```python
import torch

def _softmax(x, axis=-1):
    return torch.softmax(x, dim=axis)
def _gelu(x):
    return torch.nn.functional.gelu(x, approximate="tanh")
def _silu(x):
    return torch.nn.functional.silu(x)
def _sigmoid(x):
    return torch.sigmoid(x)
def _layernorm(x, axis=-1, eps=1e-5):
    m = x.mean(dim=axis, keepdim=True)
    v = x.var(dim=axis, keepdim=True, unbiased=False)
    return (x - m) / torch.sqrt(v + eps)
def _scatter_add(tgt, idx, src, axis=0):
    return tgt.clone().index_add_(axis, idx, src)
def _segment_sum(src, seg, n):
    out = torch.zeros((n,) + src.shape[1:], dtype=src.dtype)
    return out.index_add_(0, seg, src)
def _pad(x, pw):
    flat = tuple(v for pair in reversed(pw) for v in pair)
    return torch.nn.functional.pad(x, flat)

kernel_name = 'parallel_sum__spectral_fnet__swiglu_ffn__prompt'

def setup_inputs():

    _w = (lambda a: (lambda t: t.to(torch.bfloat16) if t.is_floating_point() else t)(torch.as_tensor(a)))
    def _A_setup():
        B, S, D = 1, 2048, 640
        ns = torch.arange(S)[:, None] * torch.arange(S)[None, :]
        nd = torch.arange(D)[:, None] * torch.arange(D)[None, :]
        Ws_re = torch.cos(-2.0 * torch.pi * ns / S).to(float)
        Ws_im = torch.sin(-2.0 * torch.pi * ns / S).to(float)
        Wd_re = torch.cos(-2.0 * torch.pi * nd / D).to(float)
        Wd_im = torch.sin(-2.0 * torch.pi * nd / D).to(float)
        return {
            "x": _w((lambda *s: torch.randn(*s, dtype=torch.bfloat16) * 0.05)(B, S, D)),
            "dft_seq_re": _w(Ws_re),
            "dft_seq_im": _w(Ws_im),
            "dft_hid_re": _w(Wd_re),
            "dft_hid_im": _w(Wd_im),
        }
    _A_in = _A_setup()

    def _B_setup():
        B, S, D, F = 1, 2048, 640, 1728
        return {
            "x": _w((lambda *s: torch.randn(*s, dtype=torch.bfloat16) * 0.05)(B, S, D)),
            "w_gate": _w((lambda *s: torch.randn(*s, dtype=torch.bfloat16) * 0.2)(D, F)),
            "w_up": _w((lambda *s: torch.randn(*s, dtype=torch.bfloat16) * 0.2)(D, F)),
            "w_down": _w((lambda *s: torch.randn(*s, dtype=torch.bfloat16) * 0.2)(F, D)),
        }
    _B_in = _B_setup()

    return {
        "A_x": _A_in["x"],
        "A_dft_seq_re": _A_in["dft_seq_re"],
        "A_dft_seq_im": _A_in["dft_seq_im"],
        "A_dft_hid_re": _A_in["dft_hid_re"],
        "A_dft_hid_im": _A_in["dft_hid_im"],
        "B_x": _B_in["x"],
        "B_w_gate": _B_in["w_gate"],
        "B_w_up": _B_in["w_up"],
        "B_w_down": _B_in["w_down"],
    }

def reference(A_x, A_dft_seq_re, A_dft_seq_im, A_dft_hid_re, A_dft_hid_im, B_x, B_w_gate, B_w_up, B_w_down):
    def _A_ref(x, dft_seq_re, dft_seq_im, dft_hid_re, dft_hid_im):
        a = torch.einsum("bsd,ed->bse", x, dft_hid_re)
        b = torch.einsum("bsd,ed->bse", x, dft_hid_im)
        y = torch.einsum("ts,bse->bte", dft_seq_re, a) - torch.einsum("ts,bse->bte", dft_seq_im, b)
        return y

    def _B_ref(x, w_gate, w_up, w_down):
        g = _silu(x @ w_gate)
        u = x @ w_up
        return (g * u) @ w_down

    x = A_x
    xn = _layernorm(x, axis=-1)
    return x + _A_ref(xn, A_dft_seq_re, A_dft_seq_im, A_dft_hid_re, A_dft_hid_im) + _B_ref(xn, B_w_gate, B_w_up, B_w_down)
```

```cpp
#include <cuda_runtime.h>
#include <cuda_bf16.h>
#include <cuda.h>
#include <stdint.h>

namespace {

constexpr int S_ = 2048, D_ = 640, F_ = 1728;
constexpr int NCTA = 132;
constexpr int A_SLOT = 16384, RING_SLOT = 8192, RING_N = 8;
constexpr int OFF_RING = 10 * A_SLOT;
constexpr int OFF_MISC = OFF_RING + RING_N * RING_SLOT;
constexpr int ST2_BYTES = 36864, ST2_N = 6;
constexpr int OFF_BAR = OFF_MISC;
constexpr int OFF_CONST = OFF_MISC + 512;
constexpr int OFF_EPOCH = OFF_BAR + 504;
constexpr int SMEM_TOTAL = OFF_CONST + 2560;

constexpr int ZS = 2;
constexpr int ZE = 5;
constexpr int M1 = 21;
constexpr int PD = 8;
constexpr int XA = 6;
constexpr int WKA = 2;
constexpr int SW1 = 4;
constexpr int APACE = 200;
constexpr int WK = 7;
constexpr int ND = 6;
constexpr int XD0 = 10000;
constexpr int XD1 = 15000;
constexpr int PS0 = 1030;
constexpr int PS1 = 520;
constexpr int PS2 = 320;
constexpr int DS = 3;
constexpr int DF = (ZS + 2);
constexpr int PACE = 642;
constexpr int PMARG = 1400;
constexpr int PM0 = (-100);
constexpr int NFULL0 = 64 - M1 - ZE, NFULL1 = M1 - ZS + 27;
static_assert(M1 > ZS && M1 + 6 < 32 && ZS <= 6 && ZE <= 8, "schedule");

struct Params {
  CUtensorMap x, wdr, wdi, wg, wu, ab, wdn, crw, ciw;
  CUtensorMap am[5];
  const __nv_bfloat16 *xp, *wdrp, *wdip, *wgp, *wup, *crp, *cip, *wdnp;
  __nv_bfloat16* out;
};

__device__ __align__(1024) __nv_bfloat16 g_ab[2 * S_ * D_];
__device__ __align__(1024) __nv_bfloat16 g_h[S_ * F_];
__device__ __align__(128) unsigned long long g_stat[S_];
__device__ __align__(128) unsigned long long g_cs[37 * 128];
__device__ __align__(64) unsigned long long g_tc[16 * 8];
__device__ unsigned g_epoch;
__device__ __align__(128) unsigned g_cnt[160];
constexpr int CNT_A = 0, CNT_B = 1, CNT_H = 8  ;

__device__ __forceinline__ uint32_t smem_u32(const void* p) { return (uint32_t)__cvta_generic_to_shared(p); }
__device__ __forceinline__ void mbar_init(uint32_t bar, uint32_t count) { asm volatile("mbarrier.init.shared::cta.b64 [%0], %1;" ::"r"(bar), "r"(count)); }
__device__ __forceinline__ void mbar_expect_tx(uint32_t bar, uint32_t bytes) { asm volatile("mbarrier.arrive.expect_tx.shared::cta.b64 _, [%0], %1;" ::"r"(bar), "r"(bytes) : "memory"); }
__device__ __forceinline__ void mbar_arrive(uint32_t bar) { asm volatile("mbarrier.arrive.shared::cta.b64 _, [%0];" ::"r"(bar) : "memory"); }
__device__ __forceinline__ void mbar_arrive_cluster(uint32_t bar, uint32_t cta) {
  asm volatile("{\n.reg .b32 ra;\nmapa.shared::cluster.u32 ra, %0, %1;\nmbarrier.arrive.shared::cluster.b64 _, [ra];\n}" ::"r"(bar), "r"(cta) : "memory");
}
__device__ __forceinline__ void mbar_arrive_remote(uint32_t a) { asm volatile("mbarrier.arrive.shared::cluster.b64 _, [%0];" ::"r"(a) : "memory"); }
__device__ __forceinline__ void mbar_arrive_remote_n(uint32_t a, uint32_t n) { asm volatile("mbarrier.arrive.shared::cluster.b64 _, [%0], %1;" ::"r"(a), "r"(n) : "memory"); }
__device__ __forceinline__ bool mbar_try_wait(uint32_t bar, uint32_t parity) {
  uint32_t ok;
  asm volatile("{\n.reg .pred p;\nmbarrier.try_wait.parity.shared::cta.b64 p, [%1], %2;\nselp.u32 %0, 1, 0, p;\n}" : "=r"(ok) : "r"(bar), "r"(parity) : "memory");
  return ok;
}
__device__ __forceinline__ bool mbar_test(uint32_t bar, uint32_t parity) {
  uint32_t ok;
  asm volatile("{\n.reg .pred p;\nmbarrier.test_wait.parity.shared::cta.b64 p, [%1], %2;\nselp.u32 %0, 1, 0, p;\n}" : "=r"(ok) : "r"(bar), "r"(parity) : "memory");
  return ok;
}
__device__ __forceinline__ uint32_t mapa(uint32_t a, uint32_t cta) { uint32_t r; asm("mapa.shared::cluster.u32 %0, %1, %2;" : "=r"(r) : "r"(a), "r"(cta)); return r; }
__device__ __forceinline__ void mbar_wait(uint32_t bar, uint32_t parity) {
#pragma unroll 1
  for (uint32_t it = 0; it < (1u << 18); it++) { if (mbar_try_wait(bar, parity)) break; }
}
__device__ __forceinline__ void tma_2d(uint32_t dst, const CUtensorMap* tm, uint32_t bar, int c0, int c1) {
  asm volatile("cp.async.bulk.tensor.2d.shared::cluster.global.mbarrier::complete_tx::bytes [%0], [%1, {%3, %4}], [%2];"
               ::"r"(dst), "l"((uint64_t)tm), "r"(bar), "r"(c0), "r"(c1) : "memory");
}
__device__ __forceinline__ void tma_2d_mc(uint32_t dst, const CUtensorMap* tm, uint32_t bar, int c0, int c1) {
  asm volatile("cp.async.bulk.tensor.2d.shared::cluster.global.mbarrier::complete_tx::bytes.multicast::cluster [%0], [%1, {%3, %4}], [%2], %5;"
               ::"r"(dst), "l"((uint64_t)tm), "r"(bar), "r"(c0), "r"(c1), "h"((uint16_t)3) : "memory");
}
__device__ __forceinline__ void tma_4d_mc(uint32_t dst, const CUtensorMap* tm, uint32_t bar, int c2, int c3) {
  asm volatile("cp.async.bulk.tensor.4d.shared::cluster.global.mbarrier::complete_tx::bytes.multicast::cluster [%0], [%1, {%5, %5, %3, %4}], [%2], %6;"
               ::"r"(dst), "l"((uint64_t)tm), "r"(bar), "r"(c2), "r"(c3), "r"(0), "h"((uint16_t)3) : "memory");
}
__device__ __forceinline__ void tma_5d_mc(uint32_t dst, const CUtensorMap* tm, uint32_t bar, int c0, int c4) {
  asm volatile("cp.async.bulk.tensor.5d.shared::cluster.global.mbarrier::complete_tx::bytes.multicast::cluster [%0], [%1, {%3, %5, %5, %5, %4}], [%2], %6;"
               ::"r"(dst), "l"((uint64_t)tm), "r"(bar), "r"(c0), "r"(c4), "r"(0), "h"((uint16_t)3) : "memory");
}
__device__ __forceinline__ void tma_5d(uint32_t dst, const CUtensorMap* tm, uint32_t bar, int c0, int c4) {
  asm volatile("cp.async.bulk.tensor.5d.shared::cluster.global.mbarrier::complete_tx::bytes [%0], [%1, {%3, %5, %5, %5, %4}], [%2];"
               ::"r"(dst), "l"((uint64_t)tm), "r"(bar), "r"(c0), "r"(c4), "r"(0) : "memory");
}
__device__ __forceinline__ uint64_t policy_evict_first() { uint64_t p; asm volatile("createpolicy.fractional.L2::evict_first.b64 %0, 1.0;" : "=l"(p)); return p; }
__device__ __forceinline__ void tma_2d_h(uint32_t dst, const CUtensorMap* tm, uint32_t bar, int c0, int c1, uint64_t pol) {
  asm volatile("cp.async.bulk.tensor.2d.shared::cluster.global.mbarrier::complete_tx::bytes.L2::cache_hint [%0], [%1, {%3, %4}], [%2], %5;"
               ::"r"(dst), "l"((uint64_t)tm), "r"(bar), "r"(c0), "r"(c1), "l"(pol) : "memory");
}
__device__ __forceinline__ void tma_prefetch_2d(const CUtensorMap* tm, int c0, int c1) {
  asm volatile("cp.async.bulk.prefetch.tensor.2d.L2.global [%0, {%1, %2}];" ::"l"((uint64_t)tm), "r"(c0), "r"(c1) : "memory");
}
__device__ __forceinline__ void tma_prefetch_5d(const CUtensorMap* tm, int c0, int c4) {
  asm volatile("cp.async.bulk.prefetch.tensor.5d.L2.global [%0, {%1, %3, %3, %3, %2}];" ::"l"((uint64_t)tm), "r"(c0), "r"(c4), "r"(0) : "memory");
}
__device__ __forceinline__ void red_add_bf16x8(void* p, uint4 v) {
  asm volatile("red.relaxed.gpu.global.add.noftz.v4.bf16x2 [%0], {%1,%2,%3,%4};" ::"l"(p), "r"(v.x), "r"(v.y), "r"(v.z), "r"(v.w) : "memory");
}
__device__ __forceinline__ void stg128(void* p, uint32_t a, uint32_t b, uint32_t c, uint32_t d) { asm volatile("st.global.v4.u32 [%0], {%1,%2,%3,%4};" ::"l"(p), "r"(a), "r"(b), "r"(c), "r"(d)); }
__device__ __forceinline__ void sts128(uint32_t a, uint4 v) { asm volatile("st.shared.v4.u32 [%0], {%1,%2,%3,%4};" ::"r"(a), "r"(v.x), "r"(v.y), "r"(v.z), "r"(v.w) : "memory"); }
__device__ __forceinline__ bool elect_one() {
  uint32_t pred;
  asm volatile("{\n.reg .pred p;\nelect.sync _|p, 0xffffffff;\nselp.u32 %0, 1, 0, p;\n}" : "=r"(pred));
  return pred;
}
__device__ __forceinline__ void prefetch_tmap(const CUtensorMap* tm) { asm volatile("prefetch.tensormap [%0];" ::"l"((uint64_t)tm) : "memory"); }
__device__ __forceinline__ void prefetch_l2(const void* p, uint32_t bytes) { asm volatile("cp.async.bulk.prefetch.L2.global [%0], %1;" ::"l"(p), "r"(bytes) : "memory"); }
__device__ __forceinline__ void wgmma_fence() { asm volatile("wgmma.fence.sync.aligned;" ::: "memory"); }
__device__ __forceinline__ void wgmma_commit() { asm volatile("wgmma.commit_group.sync.aligned;" ::: "memory"); }
template <int N> __device__ __forceinline__ void wgmma_wait() { asm volatile("wgmma.wait_group.sync.aligned %0;" ::"n"(N) : "memory"); }
template <int R> __device__ __forceinline__ void reg_alloc() { asm volatile("setmaxnreg.inc.sync.aligned.u32 %0;" ::"n"(R)); }
template <int R> __device__ __forceinline__ void reg_dealloc() { asm volatile("setmaxnreg.dec.sync.aligned.u32 %0;" ::"n"(R)); }
__device__ __forceinline__ void bar_sync(int id, int n) { asm volatile("bar.sync %0, %1;" ::"r"(id), "r"(n) : "memory"); }
__device__ __forceinline__ void bar_arrive(int id, int n) { asm volatile("bar.arrive %0, %1;" ::"r"(id), "r"(n) : "memory"); }
__device__ __forceinline__ void cluster_arrive() { asm volatile("barrier.cluster.arrive.relaxed.aligned;" ::: "memory"); }
__device__ __forceinline__ void cluster_wait() { asm volatile("barrier.cluster.wait.acquire.aligned;" ::: "memory"); }
__device__ __forceinline__ void fence_proxy_async_global() { asm volatile("fence.proxy.async.global;" ::: "memory"); }
__device__ __forceinline__ unsigned ld_acquire(const unsigned* p) { unsigned v; asm volatile("ld.acquire.gpu.global.u32 %0, [%1];" : "=r"(v) : "l"(p) : "memory"); return v; }
__device__ __forceinline__ void red_release_add(unsigned* p, unsigned v) { asm volatile("red.release.gpu.global.add.u32 [%0], %1;" ::"l"(p), "r"(v) : "memory"); }
__device__ __forceinline__ void st_tagged(unsigned long long* p, uint32_t v, uint32_t tag) {
  asm volatile("st.relaxed.gpu.global.u64 [%0], %1;" ::"l"(p), "l"((unsigned long long)v | ((unsigned long long)tag << 32)) : "memory");
}
__device__ __forceinline__ uint4 ld_tagged2(const unsigned long long* p) {
  unsigned long long a, b; asm volatile("ld.relaxed.gpu.global.v2.u64 {%0, %1}, [%2];" : "=l"(a), "=l"(b) : "l"(p) : "memory");
  return make_uint4((uint32_t)a, (uint32_t)(a >> 32), (uint32_t)b, (uint32_t)(b >> 32));
}
__device__ __forceinline__ uint32_t clock32() { uint32_t c; asm volatile("mov.u32 %0, %%clock;" : "=r"(c)); return c; }
__device__ __forceinline__ void spin(uint32_t n) { const uint32_t t = clock32(); while (clock32() - t < n) { } }
template <typename T> __device__ __forceinline__ T* padd(T* base, uint32_t n) {
  uint64_t r;
  asm("{\n.reg .u32 l, h;\nadd.cc.u32 l, %1, %3;\naddc.u32 h, %2, 0;\nmov.b64 %0, {l, h};\n}"
      : "=l"(r) : "r"((uint32_t)(uint64_t)base), "r"((uint32_t)((uint64_t)base >> 32)), "r"(n * (uint32_t)sizeof(T)));
  return reinterpret_cast<T*>(r);
}
template <int N> struct IC { static constexpr int value = N; };
__device__ __forceinline__ void wait_cnt(const unsigned* p, unsigned target) {
#pragma unroll 1
  for (uint32_t it = 0; it < (1u << 20); it++) { if ((int)(ld_acquire(p) - target) >= 0) break; }
}
__device__ __forceinline__ void wait_cnt_slow(const unsigned* p, unsigned target) {
#pragma unroll 1
  for (uint32_t it = 0; it < (1u << 18); it++) { if ((int)(ld_acquire(p) - target) >= 0) break; __nanosleep(300); }
}
__device__ __forceinline__ void mbar_wait_long(uint32_t bar) {
#pragma unroll 1
  for (uint32_t it = 0; it < (1u << 22); it++) { if (mbar_try_wait(bar, 0)) break; }
}
template <int N> __device__ __forceinline__ void fence_acc(float (&d)[N]) {
#pragma unroll
  for (int i = 0; i < N; i++) asm volatile("" : "+f"(d[i])::"memory");
}
__device__ __forceinline__ uint32_t pack_bf16(float lo, float hi) {
  uint32_t r; asm("cvt.rn.bf16x2.f32 %0, %1, %2;" : "=r"(r) : "f"(hi), "f"(lo)); return r;
}
__device__ __forceinline__ float bf_lo(uint32_t v) { return __uint_as_float(v << 16); }
__device__ __forceinline__ float bf_hi(uint32_t v) { return __uint_as_float(v & 0xFFFF0000u); }
__device__ __forceinline__ uint4 lds128(uint32_t a) { uint4 v; asm volatile("ld.shared.v4.u32 {%0,%1,%2,%3}, [%4];" : "=r"(v.x), "=r"(v.y), "=r"(v.z), "=r"(v.w) : "r"(a) : "memory"); return v; }
__device__ __forceinline__ uint32_t lds32(uint32_t a) { uint32_t v; asm volatile("ld.shared.u32 %0, [%1];" : "=r"(v) : "r"(a) : "memory"); return v; }
__device__ __forceinline__ void sts32(uint32_t a, uint32_t v) { asm volatile("st.shared.u32 [%0], %1;" ::"r"(a), "r"(v) : "memory"); }
__device__ __forceinline__ uint4 ldg_nc128(const void* p) { uint4 v; asm volatile("ld.global.nc.L1::no_allocate.v4.u32 {%0,%1,%2,%3}, [%4];" : "=r"(v.x), "=r"(v.y), "=r"(v.z), "=r"(v.w) : "l"(p)); return v; }

__device__ __forceinline__ uint64_t mk_desc(uint32_t lo, uint32_t hi) { uint64_t d; asm("mov.b64 %0, {%1, %2};" : "=l"(d) : "r"(lo), "r"(hi)); return d; }
constexpr uint32_t HI_128 = (1024 >> 4) | (1u << 30), HI_64 = (512 >> 4) | (2u << 30);
constexpr uint32_t LBO_K = 1u << 16, LBO_MN128 = (4096u >> 4) << 16, LBO_MN64 = (2048u >> 4) << 16;
constexpr uint32_t D0 = 1024 >> 4;
__device__ __forceinline__ uint64_t desc_k128(uint32_t d16) { return mk_desc(d16 + LBO_K, HI_128); }
__device__ __forceinline__ uint64_t desc_mn128(uint32_t d16) { return mk_desc(d16 + LBO_MN128, HI_128); }
__device__ __forceinline__ uint64_t desc_mn64(uint32_t d16) { return mk_desc(d16 + LBO_MN64, HI_64); }

template<int TB, int OFF> __device__ __forceinline__ void wgmma_n128(float (&d)[64], uint64_t da, uint64_t db, int scale_d) {
  asm volatile("{\n.reg .pred p;\n"
    "setp.ne.b32 p, %66, 0;\n"
    "wgmma.mma_async.sync.aligned.m64n128k16.f32.bf16.bf16 "
    "{%0, %1, %2, %3, %4, %5, %6, %7, %8, %9, %10, %11, %12, %13, %14, %15, "
    "%16, %17, %18, %19, %20, %21, %22, %23, %24, %25, %26, %27, %28, %29, %30, %31, "
    "%32, %33, %34, %35, %36, %37, %38, %39, %40, %41, %42, %43, %44, %45, %46, %47, "
    "%48, %49, %50, %51, %52, %53, %54, %55, %56, %57, %58, %59, %60, %61, %62, %63}, "
    "%64, %65, p, 1, 1, 0, %67;\n}\n"
    : "+f"(d[OFF+0]), "+f"(d[OFF+1]), "+f"(d[OFF+2]), "+f"(d[OFF+3]), "+f"(d[OFF+4]), "+f"(d[OFF+5]), "+f"(d[OFF+6]), "+f"(d[OFF+7]),
      "+f"(d[OFF+8]), "+f"(d[OFF+9]), "+f"(d[OFF+10]), "+f"(d[OFF+11]), "+f"(d[OFF+12]), "+f"(d[OFF+13]), "+f"(d[OFF+14]), "+f"(d[OFF+15]),
      "+f"(d[OFF+16]), "+f"(d[OFF+17]), "+f"(d[OFF+18]), "+f"(d[OFF+19]), "+f"(d[OFF+20]), "+f"(d[OFF+21]), "+f"(d[OFF+22]), "+f"(d[OFF+23]),
      "+f"(d[OFF+24]), "+f"(d[OFF+25]), "+f"(d[OFF+26]), "+f"(d[OFF+27]), "+f"(d[OFF+28]), "+f"(d[OFF+29]), "+f"(d[OFF+30]), "+f"(d[OFF+31]),
      "+f"(d[OFF+32]), "+f"(d[OFF+33]), "+f"(d[OFF+34]), "+f"(d[OFF+35]), "+f"(d[OFF+36]), "+f"(d[OFF+37]), "+f"(d[OFF+38]), "+f"(d[OFF+39]),
      "+f"(d[OFF+40]), "+f"(d[OFF+41]), "+f"(d[OFF+42]), "+f"(d[OFF+43]), "+f"(d[OFF+44]), "+f"(d[OFF+45]), "+f"(d[OFF+46]), "+f"(d[OFF+47]),
      "+f"(d[OFF+48]), "+f"(d[OFF+49]), "+f"(d[OFF+50]), "+f"(d[OFF+51]), "+f"(d[OFF+52]), "+f"(d[OFF+53]), "+f"(d[OFF+54]), "+f"(d[OFF+55]),
      "+f"(d[OFF+56]), "+f"(d[OFF+57]), "+f"(d[OFF+58]), "+f"(d[OFF+59]), "+f"(d[OFF+60]), "+f"(d[OFF+61]), "+f"(d[OFF+62]), "+f"(d[OFF+63])
    : "l"(da), "l"(db), "r"(scale_d), "n"(TB));
}
template<int TB, int OFF> __device__ __forceinline__ void wgmma_n160(float (&d)[80], uint64_t da, uint64_t db, int scale_d) {
  asm volatile("{\n.reg .pred p;\n"
    "setp.ne.b32 p, %82, 0;\n"
    "wgmma.mma_async.sync.aligned.m64n160k16.f32.bf16.bf16 "
    "{%0, %1, %2, %3, %4, %5, %6, %7, %8, %9, %10, %11, %12, %13, %14, %15, "
    "%16, %17, %18, %19, %20, %21, %22, %23, %24, %25, %26, %27, %28, %29, %30, %31, "
    "%32, %33, %34, %35, %36, %37, %38, %39, %40, %41, %42, %43, %44, %45, %46, %47, "
    "%48, %49, %50, %51, %52, %53, %54, %55, %56, %57, %58, %59, %60, %61, %62, %63, "
    "%64, %65, %66, %67, %68, %69, %70, %71, %72, %73, %74, %75, %76, %77, %78, %79}, "
    "%80, %81, p, 1, 1, 0, %83;\n}\n"
    : "+f"(d[OFF+0]), "+f"(d[OFF+1]), "+f"(d[OFF+2]), "+f"(d[OFF+3]), "+f"(d[OFF+4]), "+f"(d[OFF+5]), "+f"(d[OFF+6]), "+f"(d[OFF+7]),
      "+f"(d[OFF+8]), "+f"(d[OFF+9]), "+f"(d[OFF+10]), "+f"(d[OFF+11]), "+f"(d[OFF+12]), "+f"(d[OFF+13]), "+f"(d[OFF+14]), "+f"(d[OFF+15]),
      "+f"(d[OFF+16]), "+f"(d[OFF+17]), "+f"(d[OFF+18]), "+f"(d[OFF+19]), "+f"(d[OFF+20]), "+f"(d[OFF+21]), "+f"(d[OFF+22]), "+f"(d[OFF+23]),
      "+f"(d[OFF+24]), "+f"(d[OFF+25]), "+f"(d[OFF+26]), "+f"(d[OFF+27]), "+f"(d[OFF+28]), "+f"(d[OFF+29]), "+f"(d[OFF+30]), "+f"(d[OFF+31]),
      "+f"(d[OFF+32]), "+f"(d[OFF+33]), "+f"(d[OFF+34]), "+f"(d[OFF+35]), "+f"(d[OFF+36]), "+f"(d[OFF+37]), "+f"(d[OFF+38]), "+f"(d[OFF+39]),
      "+f"(d[OFF+40]), "+f"(d[OFF+41]), "+f"(d[OFF+42]), "+f"(d[OFF+43]), "+f"(d[OFF+44]), "+f"(d[OFF+45]), "+f"(d[OFF+46]), "+f"(d[OFF+47]),
      "+f"(d[OFF+48]), "+f"(d[OFF+49]), "+f"(d[OFF+50]), "+f"(d[OFF+51]), "+f"(d[OFF+52]), "+f"(d[OFF+53]), "+f"(d[OFF+54]), "+f"(d[OFF+55]),
      "+f"(d[OFF+56]), "+f"(d[OFF+57]), "+f"(d[OFF+58]), "+f"(d[OFF+59]), "+f"(d[OFF+60]), "+f"(d[OFF+61]), "+f"(d[OFF+62]), "+f"(d[OFF+63]),
      "+f"(d[OFF+64]), "+f"(d[OFF+65]), "+f"(d[OFF+66]), "+f"(d[OFF+67]), "+f"(d[OFF+68]), "+f"(d[OFF+69]), "+f"(d[OFF+70]), "+f"(d[OFF+71]),
      "+f"(d[OFF+72]), "+f"(d[OFF+73]), "+f"(d[OFF+74]), "+f"(d[OFF+75]), "+f"(d[OFF+76]), "+f"(d[OFF+77]), "+f"(d[OFF+78]), "+f"(d[OFF+79])
    : "l"(da), "l"(db), "r"(scale_d), "n"(TB));
}

__device__ __forceinline__ void wgmma_n8_ta(float (&d)[4], uint64_t da, uint64_t db, int scale_d) {
  asm volatile("{\n.reg .pred p;\nsetp.ne.b32 p, %6, 0;\n"
               "wgmma.mma_async.sync.aligned.m64n8k16.f32.bf16.bf16 {%0, %1, %2, %3}, %4, %5, p, 1, 1, 1, 0;\n}\n"
               : "+f"(d[0]), "+f"(d[1]), "+f"(d[2]), "+f"(d[3]) : "l"(da), "l"(db), "r"(scale_d));
}

__device__ __forceinline__ uint4 quad_transpose(uint32_t p0, uint32_t p1, uint32_t p2, uint32_t p3, int q) {
  bool b0 = q & 1, b1 = q & 2;
  uint32_t a = b0 ? p0 : p1, b = b0 ? p2 : p3;
  uint32_t ra = __shfl_xor_sync(0xffffffffu, a, 1), rb = __shfl_xor_sync(0xffffffffu, b, 1);
  uint32_t u0 = b0 ? ra : p0, u1 = b0 ? p1 : ra, v0 = b0 ? rb : p2, v1 = b0 ? p3 : rb;
  uint32_t s0 = b1 ? u0 : v0, s1 = b1 ? u1 : v1;
  uint32_t r0 = __shfl_xor_sync(0xffffffffu, s0, 2), r1 = __shfl_xor_sync(0xffffffffu, s1, 2);
  uint4 o;
  o.x = b1 ? r0 : u0; o.y = b1 ? r1 : u1; o.z = b1 ? v0 : r0; o.w = b1 ? v1 : r1;
  return o;
}

__device__ __forceinline__ float rcp_approx(float v) { float r; asm("rcp.approx.ftz.f32 %0, %1;" : "=f"(r) : "f"(v)); return r; }
__device__ __forceinline__ float round_bf16(float v) { return bf_lo(pack_bf16(v, 0.f)); }
__device__ __forceinline__ float swiglu(float tg, float tu, float re, float ve) {
  float e; asm("ex2.approx.ftz.f32 %0, %1;" : "=f"(e) : "f"(tg * re));
  float r; asm("rcp.approx.ftz.f32 %0, %1;" : "=f"(r) : "f"(fmaf(e, ve, ve)));
  return (tg * r) * tu;
}

__device__ __forceinline__ int stat_slot(bool extra, int i) { return extra ? i : 4; }
__device__ __forceinline__ int cs_slot(bool extra, int i) { return extra ? 4 : (i & 3); }

struct Role {
  int extra;
  int p;
  int ig;
  int ngroups;
};

__device__ __forceinline__ int group_id(const Role& r, int i) { return r.extra ? 36 : (i < 4 ? 8 * i + (r.ig ^ (i == 1 ? SW1 : 0)) : 32 + r.ig); }
__device__ __forceinline__ int group_rb(const Role& r, int i, int rank) { return 2 * (r.extra ? r.p + i : r.p) + rank; }

template <int MODE>
__device__ __forceinline__ void p1_mainloop(float (&acc0)[64], float (&acc1)[64], uint32_t sbase, int i, uint32_t a_par,
                                            bool last, bool signal_next, int wg, int tid) {
  constexpr bool GU = MODE & 1, WAITA = MODE & 2, RELA = MODE & 4;
  const uint32_t bars = sbase + OFF_BAR;
  uint32_t half = wg;
  uint32_t par = (i >> 1) & 1;
  const bool rel = (tid & 95) == 0;
  const uint32_t rel_addr = mapa(bars + 224, (tid >> 5) & 1);
  const bool rel2 = last && (tid & 95) == 64;
  uint32_t rel2_addr = mapa(bars + 336 - 8, (tid >> 5) & 1);
  uint32_t da = D0;
  uint32_t rc = GU || i ? 2 : 1;
  bool ready = false, readya = false;
#pragma unroll 1
  for (int j = 0; j < 5; j++) {
    const uint32_t db = D0 + (OFF_RING >> 4) + half * (4 * RING_SLOT >> 4);
    const uint32_t fb = bars + 160 + half * 32, fbn = bars + 160 + (half ^ 1) * 32;
    const uint32_t eb = rel_addr + half * 32, ebp = rel_addr + (half ^ 1) * 32;
    const uint32_t parn = par ^ half;
#pragma unroll
    for (int u = 0; u < 4; u++) {
      if (GU) {
        if (WAITA && !(u & 1)) mbar_wait(bars + 16 * j + 4 * u, a_par);
        if (!ready) mbar_wait(fb + 8 * u, par);
        ready = u < 3 ? mbar_test(fb + 8 * u + 8, par) : mbar_test(fbn, parn);
      } else if (!(u & 1)) {
        if (WAITA && !readya) mbar_wait(bars + 16 * j + 4 * u, a_par);
        if (!ready) mbar_wait(fb + 8 * u, par);
      } else {
        if (WAITA) readya = mbar_test(bars + 16 * j + 4 * u + 4, a_par);
        ready = mbar_test(u == 1 ? fb + 16 : fbn, u == 1 ? par : parn);
      }
      wgmma_fence();
#pragma unroll
      for (int kk = 0; kk < 2; kk++) {
        const uint32_t a = da + (u >> 1) * (A_SLOT >> 4) + (u & 1) * 4 + kk * 2;
        const uint64_t b = GU ? desc_mn128(db + u * (RING_SLOT >> 4) + kk * 128) : desc_k128(db + (u >> 1) * (2 * RING_SLOT >> 4) + (u & 1) * 4 + kk * 2);
        const int sc = (u | kk) != 0 || j != 0;
        wgmma_n128<GU ? 1 : 0, 0>(acc0, desc_k128(a), b, sc);
        wgmma_n128<GU ? 1 : 0, 0>(acc1, desc_k128(a + 512), b, sc);
      }
      wgmma_commit();
      if (u == 3 && j == 4 && signal_next) bar_arrive(1 + (wg ^ 1), 256);
      wgmma_wait<2>();
      if (GU) {
        if (u >= 2) { if (rel) mbar_arrive_remote_n(eb + 8 * (u - 2), rc); }
        else if (rel && j) mbar_arrive_remote_n(ebp + 8 * (u + 2), rc);
      } else if (u == 3) {
        if (rel) { mbar_arrive_remote_n(eb, rc); mbar_arrive_remote_n(eb + 8, rc); }
        if (j == WK / 2) rc = 2;
      } else if (u == 1) {
        if (rel && j) { mbar_arrive_remote_n(ebp + 16, rc); mbar_arrive_remote_n(ebp + 24, rc); }
      }
      if (u == 3) { if (rel2 && j) mbar_arrive_remote(rel2_addr); rel2_addr += 8; }
      if (RELA && tid == 64 && (u & 1) && (u == 3 || j)) mbar_arrive(bars + 80 + 16 * j + 4 * u - 12);
    }
    da += 2 * (A_SLOT >> 4);
    par = parn; half ^= 1;
  }
  const uint32_t ebp = rel_addr + (half ^ 1) * 32;
  if (GU) { wgmma_wait<1>(); if (rel) mbar_arrive_remote_n(ebp + 16, rc); }
  wgmma_wait<0>();
  fence_acc(acc0); fence_acc(acc1);
  if (rel) { if (!GU) mbar_arrive_remote_n(ebp + 16, rc); mbar_arrive_remote_n(ebp + 24, rc); }
  if (RELA && tid == 64) mbar_arrive(bars + 80 + 72);
}

template <int JH, int R, int NA = 64>
__device__ __forceinline__ void gu_chunk(const float (&a)[NA], uint32_t st, const float* csq, __nv_bfloat16* dst) {
  const float nm = -bf_lo(st), ve = bf_hi(st) * bf_hi(st), re = -1.4426950408889634f * rcp_approx(bf_hi(st));
  uint32_t pk[4];
#pragma unroll
  for (int k = 0; k < 4; k++) {
    constexpr int UO = NA / 2;
    const int o = ((NA == 64 ? JH * 4 : 0) + k) * 4 + R * 2;
    const float2 cg = *reinterpret_cast<const float2*>(csq + (JH * 4 + k) * 8), cu = *reinterpret_cast<const float2*>(csq + 64 + (JH * 4 + k) * 8);
    pk[k] = pack_bf16(swiglu(fmaf(nm, cg.x, a[o]), fmaf(nm, cu.x, a[o + UO]), re, ve), swiglu(fmaf(nm, cg.y, a[o + 1]), fmaf(nm, cu.y, a[o + UO + 1]), re, ve));
  }
  stg128(dst + (R * 8) * F_ + JH * 32, pk[0], pk[1], pk[2], pk[3]);
}

__global__ void __cluster_dims__(2, 1, 1) __launch_bounds__(384, 1) fused_kernel(const __grid_constant__ Params P) {
  extern __shared__ __align__(1024) uint8_t smem_raw[];
  if (threadIdx.x == 0) { prefetch_tmap(&P.x); prefetch_tmap(&P.wdr); prefetch_tmap(&P.wdi); }
  uint32_t sbase = smem_u32(smem_raw);
  if ((sbase & 0xFFFFFF) != 1024) return;
  asm volatile("" : "+r"(sbase));
  const uint32_t bars = sbase + OFF_BAR;
  const uint32_t a_full = bars, a_empty = bars + 80, r_full = bars + 160, r_empty = bars + 224, s_full = bars + 288, s_empty = bars + 336,
                 ep_bar = bars + 384, cs_full = bars + 392, p_full = bars + 432;
  const int wid = __shfl_sync(0xffffffffu, (int)threadIdx.x >> 5, 0);
  const int wg = wid >> 2;
  const uint32_t rank = blockIdx.x & 1;

  Role role;
  {
    const int c = blockIdx.x >> 1, t = c - 4, u = t - 32, d = (u * 37) >> 8;
    role.ig = c < 4 ? 4 + c : t < 32 ? t >> 3 : t < 60 ? 4 + d : 8;
    role.p = c < 4 ? 0 : t < 32 ? t & 7 : t < 60 ? 1 + u - 7 * d : 4 * (t - 60);
  }
  role.extra = role.ig == 8;
  role.ngroups = role.ig < 4 ? 5 : 4;

  auto load_w = [&](int kb, int ch) {
    const uint32_t dst = sbase + kb * A_SLOT, fb = a_full + 8 * kb;
    mbar_expect_tx(fb, A_SLOT);
    tma_2d(dst, &P.wg, fb, ch * 64, kb * 64);
    tma_2d(dst + 4096, &P.wg, fb, ch * 64, kb * 64 + 32);
    tma_2d(dst + 8192, &P.wu, fb, ch * 64, kb * 64);
    tma_2d(dst + 12288, &P.wu, fb, ch * 64, kb * 64 + 32);
  };
  if (wid == 4) {
    if (elect_one()) {
#pragma unroll
      for (int b = 0; b < 10; b++) mbar_init(a_full + 8 * b, 1);
#pragma unroll
      for (int b = 0; b < 8; b++) mbar_init(r_full + 8 * b, 1);
      asm volatile("fence.mbarrier_init.release.cluster;" ::: "memory");
    }
    __syncwarp();
    cluster_arrive();
    if (elect_one()) {
      if (!role.extra) {
        const int xr = (2 * role.p + rank) * 128, wc = (role.ig - (role.ig < 5 ? 0 : 5)) * 4;
        const CUtensorMap* tw = role.ig < 5 ? &P.wdr : &P.wdi;
#pragma unroll 1
        for (int kb = 0; kb < XA; kb++) {
          mbar_expect_tx(a_full + 8 * kb, A_SLOT);
          tma_2d(sbase + kb * A_SLOT, &P.x, a_full + 8 * kb, kb * 64, xr);
          if (kb < 4) {
            const uint32_t dst = sbase + OFF_RING + kb * 2 * RING_SLOT, fb = r_full + 16 * kb;
            mbar_expect_tx(fb, 2 * RING_SLOT);
            tma_5d(dst, tw, fb, kb * 64, wc);
            tma_5d(dst + RING_SLOT, tw, fb, kb * 64, wc + 2);
            mbar_arrive(fb + 8);
          }
        }
        const int rb = 2 * role.p + rank;
        if (rb < 12) tma_prefetch_5d(tw, (4 + (rb >> 1)) * 64, wc + (rb & 1) * 2);
      } else {
#pragma unroll 1
        for (int kb = 0; kb < 10; kb++) load_w(kb, blockIdx.x & 3);
#pragma unroll 1
        for (int m = 0; m < 8; m++) {
          const uint32_t dst = sbase + OFF_RING + m * RING_SLOT;
          mbar_expect_tx(r_full + 8 * m, RING_SLOT);
          tma_2d(dst, &P.wg, r_full + 8 * m, 26 * 64, m * 32);
          tma_2d(dst + 4096, &P.wu, r_full + 8 * m, 26 * 64, m * 32);
        }
      }
    }
    __syncwarp();
  } else {
    if (wid == 9 && elect_one()) {
#pragma unroll
      for (int b = 10; b < 55; b++) if (b < 20 || b >= 28) mbar_init(bars + 8 * b, ((b >= 28 && b < 36) || (b >= 42 && b < 48)) ? 4 : 1);
      asm volatile("fence.mbarrier_init.release.cluster;" ::: "memory");
    }
    __syncwarp();
    cluster_arrive();
  }
  if (wg == 2) {
    reg_dealloc<40>();
    const int lane = threadIdx.x & 31;
    unsigned epoch = 0;
    if (wid == 11) epoch = *(volatile unsigned*)&g_epoch;
    cluster_wait();
    if (wid == 8 || wid == 10) {
      const int odd = (wid >> 1) & 1;
      const uint32_t dst0 = sbase + OFF_RING;
#pragma unroll 1
      for (int i = 0; i < role.ngroups; i++) {
        const int gid = group_id(role, i);
        const bool gu = gid >= 10;
        const CUtensorMap* tm = gu ? (rank ? &P.wu : &P.wg) : (gid < 5 ? &P.wdr : &P.wdi);
        const int cc = gu ? (gid - 10) * 64 : (gid % 5) * 4 + rank * 2;
        auto load_slot = [&](uint32_t slot, int n) {
          if (gu) {
            mbar_expect_tx(r_full + 8 * slot, RING_SLOT);
            tma_2d_mc(dst0 + slot * RING_SLOT + rank * 4096, tm, r_full + 8 * slot, cc, n * 32);
          } else {
            if (odd) mbar_arrive(r_full + 8 * slot); else mbar_expect_tx(r_full + 8 * slot, 2 * RING_SLOT);
            if (odd == (int)rank) tma_5d_mc(dst0 + slot * RING_SLOT, tm, r_full + 8 * (slot & 6), (n >> 1) * 64, cc);
          }
        };
        int n = odd + (i == 0 ? 8 : 0);
#pragma unroll 1
        for (; n < 20; n += 2) {
          const uint32_t it = 20 * i + n, slot = it & 7;
          mbar_wait(r_empty + 8 * slot, ((it >> 3) & 1) ^ 1);
          if (elect_one()) {
            load_slot(slot, n);
            const int kb = (n >> 1) + XA - 4;
            if (i == 0 && !role.extra && odd == (int)rank && kb < 10) {
              mbar_expect_tx(a_full + 8 * kb, A_SLOT);
              tma_2d(sbase + kb * A_SLOT, &P.x, a_full + 8 * kb, kb * 64, (2 * role.p + rank) * 128);
            }
          }
          __syncwarp();
        }
      }
      if (!role.extra) {
        mbar_wait(ep_bar, 0);
        const unsigned e1 = lds32(sbase + OFF_EPOCH) + 1;
        const unsigned* ch = &g_cnt[CNT_H + 8 * (2 * role.p + rank)];
        if (!odd) {
          const uint32_t xo = ((2 * role.p + rank) * 128 + role.ig * 16) * D_ + lane * 8;
          const __nv_bfloat16* xs = padd(P.xp, xo);
          __nv_bfloat16* xd = padd(P.out, xo);
          { const uint32_t t0 = clock32(), dl = role.ig < 4 ? XD0 : XD1; while (clock32() - t0 < dl) __nanosleep(500); }
#pragma unroll 1
          for (int m = 0; m < 10; m++) {
            const uint4 v0 = ldg_nc128(xs), v1 = ldg_nc128(xs + 256), v2 = ldg_nc128(xs + 512), v3 = ldg_nc128(xs + 768);
            stg128(xd, v0.x, v0.y, v0.z, v0.w); stg128(xd + 256, v1.x, v1.y, v1.z, v1.w);
            stg128(xd + 512, v2.x, v2.y, v2.z, v2.w); stg128(xd + 768, v3.x, v3.y, v3.z, v3.w);
            xs += 1024; xd += 1024;
          }
          __syncwarp();
          if (lane == 0) red_release_add(const_cast<unsigned*>(ch) + 3, 1);
          wait_cnt_slow(ch + 3, e1 * 8u);
          __syncwarp();
          if (lane == 0) mbar_arrive(p_full);
        } else {
          if (role.ig >= 4) {
            wait_cnt_slow(ch, e1 * 18u); __syncwarp(); if (lane == 0) mbar_arrive(a_empty);
            wait_cnt_slow(ch + 1, e1 * 8u); __syncwarp(); if (lane == 0) mbar_arrive(a_empty + 8);
            wait_cnt_slow(ch + 2, e1);
          }
          wait_cnt_slow(&g_cnt[CNT_B], e1 * 84u); __syncwarp(); if (lane == 0) mbar_arrive(a_empty + 16);
        }
      }
    } else if (wid == 9) {
      if (!role.extra) {
        const int rb = 2 * role.p + rank, j = role.ig & 3, piece = role.ig >> 2;
        const uint64_t pol = policy_evict_first();
        {
          auto sum8 = [](uint4 v) { return ((bf_lo(v.x) + bf_hi(v.x)) + (bf_lo(v.y) + bf_hi(v.y))) + ((bf_lo(v.z) + bf_hi(v.z)) + (bf_lo(v.w) + bf_hi(v.w))); };
          float t0 = 0.f, t1 = 0.f;
          const uint32_t src = sbase + OFF_RING + rb * 1024 + lane * 16, rel = mapa(r_empty + 8 * (lane & 1), (lane >> 1) & 1);
          auto nat = [](int r) { return (r & ~31) | ((r & 6) << 2) | ((r >> 2) & 6) | (r & 1); };
          const int r = rb * 8 + (lane >> 3);
          const __nv_bfloat16* wt = (role.ig < 5 ? P.wdrp : P.wdip) + (uint32_t)((role.ig - (role.ig < 5 ? 0 : 5)) * 128 * D_ + WK * 64 + (lane & 7) * 8);
          const __nv_bfloat16 *wa = wt + (uint32_t)(nat(r) * D_), *wb = wt + (uint32_t)(nat(r + 4) * D_);
          auto ring = [&](int k0, int k1) {
#pragma unroll 1
            for (int kb = k0; kb < k1; kb++) {
              mbar_wait(r_full + 16 * (kb & 3), (kb >> 2) & 1);
              t0 += sum8(lds128(src + (kb & 3) * 2 * RING_SLOT)); t1 += sum8(lds128(src + (kb & 3) * 2 * RING_SLOT + 512));
              asm volatile("" ::"f"(t0), "f"(t1) : "memory");
              __syncwarp();
              if (lane < 4) mbar_arrive_remote(rel + 16 * (kb & 3));
            }
          };
          ring(0, WKA);
          {
            const uint4 va = ldg_nc128(wa), vb = ldg_nc128(wb), vc = ldg_nc128(wa + 64), vd = ldg_nc128(wb + 64);
            const uint4 ve = ldg_nc128(wa + 128), vf = ldg_nc128(wb + 128);
            ring(WKA, WK);
            t0 += sum8(va) + sum8(vc); t1 += sum8(vb) + sum8(vd);
            t0 += sum8(ve); t1 += sum8(vf);
          }
#pragma unroll
          for (int m = 1; m < 8; m <<= 1) { t0 += __shfl_xor_sync(0xffffffffu, t0, m); t1 += __shfl_xor_sync(0xffffffffu, t1, m); }
          mbar_wait(ep_bar, 0);
          epoch = lds32(sbase + OFF_EPOCH);
          if ((lane & 3) == 0) st_tagged(g_cs + role.ig * 128 + nat(r + (lane & 4)), __float_as_uint(lane & 4 ? t1 : t0), epoch + 1);
          mbar_wait(a_full + 8 * 9, 0);
          const __nv_bfloat16* ws = padd(P.wdip, (384 + 2 * blockIdx.x + (lane >> 4)) * D_ + (lane & 15) * 8);
          uint4 wv[5];
#pragma unroll
          for (int m = 0; m < 5; m++) wv[m] = ldg_nc128(ws + m * 128);
          float t = ((sum8(wv[0]) + sum8(wv[1])) + (sum8(wv[2]) + sum8(wv[3]))) + sum8(wv[4]);
#pragma unroll
          for (int m = 1; m < 16; m <<= 1) t += __shfl_xor_sync(0xffffffffu, t, m);
          if ((lane & 15) == 0) st_tagged(g_cs + 1024 + 2 * blockIdx.x + (lane >> 4), __float_as_uint(t), epoch + 1);
        }
        const int kp0 = piece ? 0 : M1;
        auto prefetch_c = [&](int kq) { tma_prefetch_2d(kq < 32 ? &P.crw : &P.ciw, (kq & 31) * 64, rb * 128 + j * 32); };
#pragma unroll 1
        for (int it = 0; it < (1 << 16); it++) {
          if (mbar_test(cs_full + 8 * (role.ngroups - 2), 0) || mbar_test(s_empty, 0)) break;
          __nanosleep(200);
        }
        if (elect_one()) {
#pragma unroll 1
          for (int kq = 0; kq < PD; kq += 4) { prefetch_c(kp0 + kq); spin(600); }
        }
        __syncwarp();
        wait_cnt(&g_cnt[CNT_A], (epoch + 1) * 80u);
        fence_proxy_async_global();
        uint32_t tsch;
        {
          const unsigned long long* tc = padd(g_tc, (role.p * 2 + piece) * 8 + (lane & 7));
          unsigned long long v;
#pragma unroll 1
          for (int it = 0; it < (1 << 16); it++) {
            asm volatile("ld.relaxed.gpu.global.u64 %0, [%1];" : "=l"(v) : "l"(tc) : "memory");
            if (__all_sync(0xffffffffu, (uint32_t)(v >> 32) == epoch + 1)) break;
            __nanosleep(100);
          }
          const uint32_t own = __shfl_sync(0xffffffffu, (uint32_t)v, j * 2 + rank);
          int d = (int)((uint32_t)v - own);
          d = __reduce_max_sync(0xffffffffu, d > 4000 ? 0 : d);
          tsch = own + (uint32_t)(d + 1600 + PM0);
          if ((int)(tsch - clock32()) > 8000) tsch = clock32();
        }
        int nl = 0;
        uint32_t s = 0, ph = 0;
        bool ready = false;
        auto run = [&](auto kind, const CUtensorMap* ta, int k0, int k1, int brow0) {
          constexpr int KIND = decltype(kind)::value;
          const uint32_t boff = 16384 + rank * 10240;
          const int half = KIND < 2 ? 0 : piece ^ (KIND & 1) ^ 1;
          const CUtensorMap* tb = KIND == 1 ? &P.wdn : &P.ab;
#pragma unroll 1
          for (int kk = k0; kk < k1; kk++) {
            const uint32_t sa = sbase + s * ST2_BYTES, fb = s_full + 8 * s;
            if (!ready) mbar_wait(s_empty + 8 * s, ph);
            if (++s == ST2_N) { s = 0; ph ^= 1; }
            ready = mbar_test(s_empty + 8 * s, ph);
            if (elect_one()) {
              if (KIND != 3) while ((int)(clock32() - tsch) < 0) { }
              mbar_expect_tx(fb, KIND < 2 ? ST2_BYTES : ST2_BYTES - 8192);
              tma_2d_h(sa + half * 8192, ta, fb, kk * 64, rb * 128 + half * 64, pol);
              if (KIND == 1) tma_5d_mc(sa + boff, tb, fb, 0, (kk * 2 + rank) * 640 + j * 5);
              else tma_4d_mc(sa + boff, tb, fb, (brow0 + kk) * 8 + rank * 4, j * 5);
            }
            __syncwarp();
            nl++;
            tsch += nl < 4 ? PS0 : nl == 4 ? PS1 : nl < 6 + ZS ? PS2 : nl == 6 + ZS ? PMARG : PACE;
          }
        };
        run(IC<2>{}, &P.am[3], 0, ZS, 0);
        if (!piece) {
          run(IC<0>{}, &P.am[0], M1, M1 + 2, 0);
          if (elect_one()) prefetch_c(32);
          __syncwarp();
          run(IC<0>{}, &P.am[0], M1 + 2, 32, 0);
          mbar_wait_long(a_empty + 16); fence_proxy_async_global();
          run(IC<0>{}, &P.am[1], 0, 32 - ZE, 32);
        } else {
          run(IC<0>{}, &P.am[0], ZS, M1, 0);
          mbar_wait_long(a_empty); fence_proxy_async_global();
          run(IC<1>{}, &P.am[2], 0, 18, 0);
          mbar_wait_long(a_empty + 8); fence_proxy_async_global();
          run(IC<1>{}, &P.am[2], 18, 26, 0);
          mbar_wait_long(a_empty + 16); fence_proxy_async_global();
          run(IC<1>{}, &P.am[2], 26, 27, 0);
        }
        run(IC<3>{}, &P.am[4], 32 - ZE, 32, 32);
        if (blockIdx.x == 8 && lane == 0) *(volatile unsigned*)&g_epoch = epoch + 1;
      } else {
        const int e = blockIdx.x & 3, nr = e < 3 ? 7 : 6;
        bool ready = false;
#pragma unroll 1
        for (int r = 1; r < nr + role.ngroups; r++) {
#pragma unroll 1
          for (int kb = 0; kb < 10; kb++) {
            if (!ready) mbar_wait(a_empty + 8 * kb, (r - 1) & 1);
            ready = kb < 9 && mbar_test(a_empty + 8 * kb + 8, (r - 1) & 1);
            if (elect_one()) {
              if (r < nr) load_w(kb, 4 * r + e);
              else { mbar_expect_tx(a_full + 8 * kb, A_SLOT); tma_2d(sbase + kb * A_SLOT, &P.x, a_full + 8 * kb, kb * 64, group_rb(role, r - nr, rank) * 128); }
            }
            __syncwarp();
          }
        }
      }
    } else {
      if (lane == 0) {
        sts32(sbase + OFF_EPOCH, epoch);
        mbar_arrive(ep_bar);
      }
      if (!role.extra) {
        if (lane == 0) {
          prefetch_tmap(rank ? &P.wu : &P.wg);
          prefetch_tmap(&P.crw); prefetch_tmap(&P.ciw); prefetch_tmap(&P.ab); prefetch_tmap(&P.wdn);
#pragma unroll
          for (int m = 0; m < 5; m++) prefetch_tmap(&P.am[m]);
        }
      }
      const uint32_t tag = epoch + 1;
      auto fetch4 = [&](const unsigned long long* src, uint32_t dst) {
        uint4 v0, v1;
#pragma unroll 1
        for (int it = 0; it < (1 << 20); it++) {
          v0 = ld_tagged2(src); v1 = ld_tagged2(src + 2);
          if (__all_sync(0xffffffffu, v0.y == tag && v0.w == tag && v1.y == tag && v1.w == tag)) break;
          __nanosleep(200);
        }
        asm volatile("st.shared.v4.u32 [%0], {%1,%2,%3,%4};" ::"r"(dst), "r"(v0.x), "r"(v0.z), "r"(v1.x), "r"(v1.z) : "memory");
      };
      auto fill = [&](int i) {
        const uint32_t cb = sbase + OFF_CONST + lane * 16;
        if (role.extra) fetch4(padd(g_stat, group_rb(role, i, rank) * 128 + lane * 4), cb + stat_slot(role.extra, i) * 512);
        else fetch4(padd(g_cs, group_id(role, i) * 128 + lane * 4), cb + cs_slot(role.extra, i) * 512);
        __syncwarp();
        if (lane == 0) mbar_arrive(cs_full + 8 * i);
      };
      if (role.extra && lane == 0) red_release_add(&g_cnt[CNT_B], 1);
      {
        const unsigned long long *sa = padd(g_stat, group_rb(role, 0, rank) * 128 + lane * 4), *sb = padd(g_cs, group_id(role, 0) * 128 + lane * 4);
        uint4 v0, v1, v2, v3;
        if (!role.extra) {
          mbar_wait(a_full + 8 * 2, 0);
          if (lane == 0) prefetch_l2(P.wdip + (uint32_t)((384 + 2 * blockIdx.x) * D_), 2 * D_ * 2);
          mbar_wait(a_full + 8 * 9, 0);
        }
#pragma unroll 1
        for (int it = 0; it < (1 << 20); it++) {
          v0 = ld_tagged2(sa); v1 = ld_tagged2(sa + 2); v2 = ld_tagged2(sb); v3 = ld_tagged2(sb + 2);
          if (__all_sync(0xffffffffu, v0.y == tag && v0.w == tag && v1.y == tag && v1.w == tag && v2.y == tag && v2.w == tag && v3.y == tag && v3.w == tag)) break;
          if (role.extra) __nanosleep(200);
        }
        sts128(sbase + OFF_CONST + lane * 16 + stat_slot(role.extra, 0) * 512, make_uint4(v0.x, v0.z, v1.x, v1.z));
        sts128(sbase + OFF_CONST + lane * 16 + cs_slot(role.extra, 0) * 512, make_uint4(v2.x, v2.z, v3.x, v3.z));
        __syncwarp();
        if (lane == 0) mbar_arrive(cs_full);
      }
#pragma unroll 1
      for (int i = 0; i < role.ngroups; i++) {
        if (i + 1 < role.ngroups) fill(i + 1);
        bar_sync(6 + (i & 1), 160);
        if (lane == 0) red_release_add(padd(g_cnt, group_id(role, i) < 5 ? CNT_A : group_id(role, i) < 10 ? CNT_B : CNT_H + 8 * group_rb(role, i, rank) + (role.extra ? 2 : i == role.ngroups - 1)), 1);
        __syncwarp();
      }
    }
    __syncwarp();
    if (role.extra) { cluster_arrive(); cluster_wait(); }
  } else {
    reg_alloc<232>();
    const int tid = threadIdx.x & 127, lane = tid & 31, warp = tid >> 5, q = lane & 3;

    cluster_wait();
    const int nr = role.extra ? ((blockIdx.x & 3) < 3 ? 7 : 6) : 0;
    if (wg != role.extra) {
    if (wg == 1) {
      float sh = 0.f, s0 = 0.f, s1 = 0.f, q0 = 0.f, q1 = 0.f;
#pragma unroll 1
      for (int kb = 0; kb < 10; kb++) {
        mbar_wait(a_full + 8 * kb, 0);
        const uint4 v = lds128(sbase + kb * A_SLOT + role.ig * 2048 + tid * 16);
        if (kb == 0) {
          sh = ((bf_lo(v.x) + bf_hi(v.x)) + (bf_lo(v.y) + bf_hi(v.y))) + ((bf_lo(v.z) + bf_hi(v.z)) + (bf_lo(v.w) + bf_hi(v.w)));
          sh += __shfl_xor_sync(0xffffffffu, sh, 1); sh += __shfl_xor_sync(0xffffffffu, sh, 2); sh += __shfl_xor_sync(0xffffffffu, sh, 4);
          sh *= 1.0f / 64.0f;
        }
        float d;
        d = bf_lo(v.x) - sh; s0 += d; q0 = fmaf(d, d, q0); d = bf_hi(v.x) - sh; s1 += d; q1 = fmaf(d, d, q1);
        d = bf_lo(v.y) - sh; s0 += d; q0 = fmaf(d, d, q0); d = bf_hi(v.y) - sh; s1 += d; q1 = fmaf(d, d, q1);
        d = bf_lo(v.z) - sh; s0 += d; q0 = fmaf(d, d, q0); d = bf_hi(v.z) - sh; s1 += d; q1 = fmaf(d, d, q1);
        d = bf_lo(v.w) - sh; s0 += d; q0 = fmaf(d, d, q0); d = bf_hi(v.w) - sh; s1 += d; q1 = fmaf(d, d, q1);
        if (kb == 9) {
          float s = s0 + s1, qq = q0 + q1;
#pragma unroll
          for (int m = 1; m < 8; m <<= 1) { s += __shfl_xor_sync(0xffffffffu, s, m); qq += __shfl_xor_sync(0xffffffffu, qq, m); }
          s *= 1.0f / (float)D_;
          const float var = fmaxf(fmaf(-s, s, qq * (1.0f / (float)D_)), 0.f);
          mbar_wait(ep_bar, 0);
          float sd; asm("sqrt.approx.ftz.f32 %0, %1;" : "=f"(sd) : "f"(round_bf16(round_bf16(var) + 1e-5f)));
          if ((tid & 7) == 0) st_tagged(g_stat + (2 * role.p + rank) * 128 + role.ig * 16 + (tid >> 3), pack_bf16(sh + s, sd), lds32(sbase + OFF_EPOCH) + 1);
        }
      }
    } else {
      if (tid < 32) sts32(sbase + OFF_CONST + 3 * 512 + tid * 4, 0x3F803F80u);
      asm volatile("fence.proxy.async.shared::cta;" ::: "memory");
      bar_sync(4, 128);
      const uint64_t ones = mk_desc(D0 + ((OFF_CONST + 3 * 512) >> 4), 0);
      bool ready = false;
#pragma unroll 1
      for (int r = 0; r < nr; r++) {
        float ag[4], au[4];
#pragma unroll 1
        for (int kb = 0; kb < 10; kb++) {
          if (!ready) mbar_wait(a_full + 8 * kb, r & 1);
          ready = kb < 9 && mbar_test(a_full + 8 * kb + 8, r & 1);
          wgmma_fence();
#pragma unroll
          for (int kk = 0; kk < 4; kk++) {
            wgmma_n8_ta(ag, desc_mn128(D0 + kb * (A_SLOT >> 4) + kk * 128), ones, (kb | kk) != 0);
            wgmma_n8_ta(au, desc_mn128(D0 + kb * (A_SLOT >> 4) + 512 + kk * 128), ones, (kb | kk) != 0);
          }
          wgmma_commit();
          wgmma_wait<1>();
          if (kb && tid == 0) mbar_arrive(a_empty + 8 * (kb - 1));
        }
        wgmma_wait<0>();
        fence_acc(ag); fence_acc(au);
        if (tid == 0) mbar_arrive(a_empty + 8 * 9);
        if (r == 0) mbar_wait(ep_bar, 0);
        const uint32_t tag = lds32(sbase + OFF_EPOCH) + 1;
        unsigned long long* dst = g_cs + (10 + 4 * r + (blockIdx.x & 3)) * 128 + warp * 16 + (lane >> 2);
        st_tagged(dst + (q & 1) * 8 + (q >> 1) * 64, __float_as_uint(q == 0 ? ag[0] : q == 1 ? ag[2] : q == 2 ? au[0] : au[2]), tag);
      }
    }
    }

    __syncwarp();
    float acc0[64], acc1[64];
    float sv[32];
#pragma unroll 1
    for (int i = wg; i < role.ngroups; i += 2) {
      const int gid = group_id(role, i), rb = group_rb(role, i, rank);
      const bool last = !role.extra && i == role.ngroups - 1;
      const bool gu = gid >= 10;
      if (i > 0) bar_sync(1 + wg, 256);
      if (role.extra) p1_mainloop<7>(acc0, acc1, sbase, i, (nr + i) & 1, false, i + 1 < role.ngroups, wg, tid);
      else if (gu) p1_mainloop<1>(acc0, acc1, sbase, i, 0, last, true, wg, tid);
      else p1_mainloop<2>(acc0, acc1, sbase, i, 0, false, true, wg, tid);
      if (!role.extra && i == role.ngroups - 2) {
        if (tid < 12) mbar_arrive_cluster(s_empty + 8 * (tid >> 1), tid & 1);
        if (tid == 32) st_tagged(g_tc + (role.p * 2 + (role.ig >> 2)) * 8 + (role.ig & 3) * 2 + rank, clock32(), lds32(sbase + OFF_EPOCH) + 1);
      }
      if (last && tid < 4) mbar_arrive_cluster(s_empty + 8 * (4 + (tid >> 1)), tid & 1);
      uint32_t tp = clock32() + 300;
      mbar_wait(cs_full + 8 * i, 0);
      const int r0 = warp * 16 + (lane >> 2);
      const float* csb = reinterpret_cast<const float*>(smem_raw + OFF_CONST + cs_slot(role.extra, i) * 512);
      const uint32_t* stw = reinterpret_cast<const uint32_t*>(smem_raw + OFF_CONST + stat_slot(role.extra, i) * 512);
      if (!gu) {
        __nv_bfloat16* dst = padd(g_ab, ((gid < 5 ? 0 : S_) + rb * 128 + warp * 16) * D_ + (gid - (gid < 5 ? 0 : 5)) * 4 * 256 + lane * 8);
        float nm[4], rs[4];
#pragma unroll
        for (int r = 0; r < 4; r++) {
          const uint32_t st = stw[r0 + (r & 1) * 8 + (r >> 1) * 64];
          nm[r] = -bf_lo(st); rs[r] = (gid < 5 ? 1.0f : -1.0f) * rcp_approx(bf_hi(st));
        }
#pragma unroll
        for (int jh = 0; jh < 4; jh++) {
          const float4 c0 = *reinterpret_cast<const float4*>(csb + jh * 32 + q * 8), c1 = *reinterpret_cast<const float4*>(csb + jh * 32 + q * 8 + 4);
          const float c[8] = {c0.x, c0.y, c0.z, c0.w, c1.x, c1.y, c1.z, c1.w};
#pragma unroll
          for (int r = 0; r < 4; r++) {
            uint32_t pk[4];
#pragma unroll
            for (int k = 0; k < 4; k++) {
              const int o = (jh * 4 + k) * 4 + (r & 1) * 2;
              const float v0 = (r < 2 ? acc0[o] : acc1[o]), v1 = (r < 2 ? acc0[o + 1] : acc1[o + 1]);
              pk[k] = pack_bf16(fmaf(nm[r], c[2 * k], v0) * rs[r], fmaf(nm[r], c[2 * k + 1], v1) * rs[r]);
            }
            stg128(dst + ((r & 1) * 8 + (r >> 1) * 64) * D_ + jh * 256, pk[0], pk[1], pk[2], pk[3]);
            if (jh * 4 + r < 15) { tp += APACE; asm volatile("" ::: "memory"); while ((int)(clock32() - tp) < 0) { } asm volatile("" ::: "memory"); }
          }
        }
      } else {
        __nv_bfloat16* dst = padd(g_h, (rb * 128 + r0) * F_ + (gid - 10) * 64 + q * 8);
        gu_chunk<0, 0>(acc0, stw[r0], csb + 2 * q, dst); gu_chunk<0, 1>(acc0, stw[r0 + 8], csb + 2 * q, dst);
        if (last) {
#pragma unroll
          for (int m = 0; m < 16; m++) { asm volatile("mov.b32 %0, %1;" : "=f"(sv[m]) : "f"(acc0[16 + m])); asm volatile("mov.b32 %0, %1;" : "=f"(sv[16 + m]) : "f"(acc0[48 + m])); }
          break;
        }
        gu_chunk<1, 0>(acc0, stw[r0], csb + 2 * q, dst); gu_chunk<1, 1>(acc0, stw[r0 + 8], csb + 2 * q, dst);
        dst += 64 * F_;
        gu_chunk<0, 0>(acc1, stw[r0 + 64], csb + 2 * q, dst); gu_chunk<0, 1>(acc1, stw[r0 + 72], csb + 2 * q, dst);
        gu_chunk<1, 0>(acc1, stw[r0 + 64], csb + 2 * q, dst); gu_chunk<1, 1>(acc1, stw[r0 + 72], csb + 2 * q, dst);
      }
      bar_arrive(6 + wg, 160);
    }

    if (role.extra) {
      cluster_arrive(); cluster_wait();
    } else {
      const int rb = 2 * role.p + rank, j = role.ig & 3, piece = role.ig >> 2;
      const bool late = piece == wg;
      const int nfull = piece ? NFULL1 : NFULL0;
      const int nend = late ? ZS + nfull + ZE : ZS + nfull, nrel = ZS + nfull + ZE - ST2_N;
      uint32_t rel_addr = (tid & 95) == 0 ? mapa(s_empty, (tid >> 5) & 1) : 0u;
      asm volatile("" : "+r"(rel_addr));
      float acc[80];
#pragma unroll
      for (int i = 0; i < 80; i++) acc[i] = 0.f;
      fence_acc(acc);
      bar_sync(late ? 3 : 1 + wg, 256);
      int s = late ? ZS % ST2_N : 0; uint32_t ph = late ? ZS / ST2_N : 0;
      bool ready = false;
      const bool rel = rel_addr != 0;
      uint32_t rcnt = 0;
#pragma unroll 1
      for (int n = late ? ZS : 0; n < nend; n++) {
        const uint32_t db = D0 + s * (ST2_BYTES >> 4) + 1024, da = db - 1024 + wg * 512;
        const int sp = s == 0 ? ST2_N - 1 : s - 1;
        if (!ready) mbar_wait(s_full + 8 * s, ph);
        if (++s == ST2_N) { s = 0; ph ^= 1; }
        ready = mbar_test(s_full + 8 * s, ph);
        wgmma_fence();
#pragma unroll
        for (int kk = 0; kk < 4; kk++) {
          wgmma_n160<1, 0>(acc, desc_k128(da + kk * 2), desc_mn64(db + (kk >> 1) * 640 + (kk & 1) * 64), 1);
        }
        wgmma_commit();
        if (n == ZS - 1) bar_arrive(3, 256);
        wgmma_wait<1>();
        if (rcnt && rel) mbar_arrive_remote_n(rel_addr + 8 * sp, rcnt);
        rcnt = n >= nrel ? 0 : (unsigned)(n - ZS) < (unsigned)nfull ? 1 : 2;
        if (late && (unsigned)(n - DF) < (unsigned)(ND * DS) && (n - DF) % DS == 0) {
          const int i = role.ngroups - 1, c = (n - DF) / DS + 8 - ND, r0 = (c >> 2) * 64 + warp * 16 + (lane >> 2);
          const float* csq = reinterpret_cast<const float*>(smem_raw + OFF_CONST + cs_slot(false, i) * 512) + 2 * q;
          const uint32_t st = reinterpret_cast<const uint32_t*>(smem_raw + OFF_CONST + 4 * 512)[r0 + (c & 1) * 8];
          __nv_bfloat16* dst = padd(g_h, (rb * 128 + r0) * F_ + (group_id(role, i) - 10) * 64 + q * 8);
          if (c == 2) gu_chunk<1, 0, 32>(sv, st, csq, dst);
          else if (c == 3) gu_chunk<1, 1, 32>(sv, st, csq, dst);
          else if (c == 4) gu_chunk<0, 0>(acc1, st, csq, dst);
          else if (c == 5) gu_chunk<0, 1>(acc1, st, csq, dst);
          else if (c == 6) gu_chunk<1, 0>(acc1, st, csq, dst);
          else { gu_chunk<1, 1>(acc1, st, csq, dst); bar_arrive(6 + wg, 160); }
        }
      }
      const bool xok = mbar_test(p_full, 0);
      wgmma_wait<0>();
      fence_acc(acc);
      if (rcnt && rel) mbar_arrive_remote_n(rel_addr + 8 * (s == 0 ? ST2_N - 1 : s - 1), rcnt);
      if (!xok) mbar_wait(p_full, 0);
      {
        const bool og = lane & 4;
        __nv_bfloat16* o1 = P.out + (uint32_t)((rb * 128 + wg * 64 + warp * 16 + (lane >> 2)) * D_ + j * 160 + q * 8);
        __nv_bfloat16* o2 = P.out + (uint32_t)((rb * 128 + wg * 64 + warp * 16 + ((lane >> 2) & 6)) * D_ + j * 160 + (lane & 7) * 8);
        auto chunk = [&](int jb, int r) {
          return quad_transpose(pack_bf16(acc[16 * jb + 2 * r], acc[16 * jb + 2 * r + 1]), pack_bf16(acc[16 * jb + 4 + 2 * r], acc[16 * jb + 5 + 2 * r]),
                                pack_bf16(acc[16 * jb + 8 + 2 * r], acc[16 * jb + 9 + 2 * r]), pack_bf16(acc[16 * jb + 12 + 2 * r], acc[16 * jb + 13 + 2 * r]), q);
        };
        auto emit = [&](auto oddc) {
          constexpr int ODD = decltype(oddc)::value;
#pragma unroll
          for (int r = 0; r < 2; r++) red_add_bf16x8(o1 + r * 8 * D_ + (ODD ? 0 : 128), chunk(ODD ? 0 : 4, r));
#pragma unroll
          for (int c = ODD; c < 4; c += 2) {
#pragma unroll
            for (int r = 0; r < 2; r++) {
              const uint4 ta = chunk(c, r), tb = chunk(c + 1, r);
              uint4 rv;
              rv.x = __shfl_xor_sync(0xffffffffu, og ? ta.x : tb.x, 4); rv.y = __shfl_xor_sync(0xffffffffu, og ? ta.y : tb.y, 4);
              rv.z = __shfl_xor_sync(0xffffffffu, og ? ta.z : tb.z, 4); rv.w = __shfl_xor_sync(0xffffffffu, og ? ta.w : tb.w, 4);
              red_add_bf16x8(o2 + r * 8 * D_ + c * 32, og ? rv : ta);
              red_add_bf16x8(o2 + (r * 8 + 1) * D_ + c * 32, og ? tb : rv);
            }
          }
        };
        if (j & 1) emit(IC<1>{}); else emit(IC<0>{});
      }
    }
  }
}

__device__ __nv_bfloat16 g_xn[S_ * D_];
__device__ __forceinline__ float rbf(float v) { return __bfloat162float(__float2bfloat16(v)); }
__global__ void fb_ln(const __nv_bfloat16* x) {
  const __nv_bfloat16* r = x + (size_t)blockIdx.x * D_;
  float s = 0.f, q = 0.f;
  for (int i = threadIdx.x; i < D_; i += 32) s += __bfloat162float(r[i]);
  for (int m = 16; m; m >>= 1) s += __shfl_xor_sync(0xffffffffu, s, m);
  s *= 1.0f / D_;
  for (int i = threadIdx.x; i < D_; i += 32) { const float d = __bfloat162float(r[i]) - s; q += d * d; }
  for (int m = 16; m; m >>= 1) q += __shfl_xor_sync(0xffffffffu, q, m);
  const float mean = rbf(s), sd = rbf(sqrtf(rbf(rbf(q * (1.0f / D_)) + 1e-5f)));
  for (int i = threadIdx.x; i < D_; i += 32) g_xn[(size_t)blockIdx.x * D_ + i] = __float2bfloat16(rbf(__bfloat162float(r[i]) - mean) / sd);
}
__device__ float fb_dot(const __nv_bfloat16* A, int K, const __nv_bfloat16* B, int sk, int sn, int m, int n) {
  __shared__ float As[16][17], Bs[16][17];
  float s = 0.f;
  for (int k0 = 0; k0 < K; k0 += 16) {
    __syncthreads();
    As[threadIdx.y][threadIdx.x] = __bfloat162float(A[(size_t)m * K + k0 + threadIdx.x]);
    Bs[threadIdx.y][threadIdx.x] = __bfloat162float(B[(size_t)(k0 + threadIdx.y) * sk + (size_t)n * sn]);
    __syncthreads();
    for (int k = 0; k < 16; k++) s = fmaf(As[threadIdx.y][k], Bs[k][threadIdx.x], s);
  }
  return s;
}
__global__ void fb_stage1(const __nv_bfloat16* wre, const __nv_bfloat16* wim, const __nv_bfloat16* wg, const __nv_bfloat16* wu) {
  const int m = blockIdx.y * 16 + threadIdx.y, n = blockIdx.x * 16 + threadIdx.x;
  if (n < 2 * D_) {
    const int im = n >= D_;
    g_ab[((size_t)im * S_ + m) * D_ + n - im * D_] = __float2bfloat16(fb_dot(g_xn, D_, im ? wim : wre, 1, D_, m, n - im * D_));
  } else {
    const float g = rbf(fb_dot(g_xn, D_, wg, F_, 1, m, n - 2 * D_)), u = rbf(fb_dot(g_xn, D_, wu, F_, 1, m, n - 2 * D_));
    g_h[(size_t)m * F_ + n - 2 * D_] = __float2bfloat16(rbf(g / (1.0f + expf(-g))) * u);
  }
}
__global__ void fb_stage2(const __nv_bfloat16* x, const __nv_bfloat16* cr, const __nv_bfloat16* ci, const __nv_bfloat16* wdn, __nv_bfloat16* out) {
  const int m = blockIdx.y * 16 + threadIdx.y, n = blockIdx.x * 16 + threadIdx.x;
  const float y = fb_dot(cr, S_, g_ab, D_, 1, m, n) - fb_dot(ci, S_, g_ab + (size_t)S_ * D_, D_, 1, m, n);
  out[(size_t)m * D_ + n] = __float2bfloat16(__bfloat162float(x[(size_t)m * D_ + n]) + y + fb_dot(g_h, F_, wdn, D_, 1, m, n));
}

typedef CUresult (*PFN_encodeTiled)(CUtensorMap*, CUtensorMapDataType, cuuint32_t, void*, const cuuint64_t*, const cuuint64_t*, const cuuint32_t*,
                                    const cuuint32_t*, CUtensorMapInterleave, CUtensorMapSwizzle, CUtensorMapL2promotion, CUtensorMapFloatOOBfill);

void make_map(PFN_encodeTiled enc, CUtensorMap* m, const void* ptr, int rank, const cuuint64_t* dims, const cuuint64_t* strides, const cuuint32_t* box,
              CUtensorMapSwizzle sw) {
  cuuint32_t es[5] = {1, 1, 1, 1, 1};
  CUresult r = enc(m, CU_TENSOR_MAP_DATA_TYPE_BFLOAT16, rank, const_cast<void*>(ptr), dims, strides, box, es, CU_TENSOR_MAP_INTERLEAVE_NONE, sw,
                   CU_TENSOR_MAP_L2_PROMOTION_L2_128B, CU_TENSOR_MAP_FLOAT_OOB_FILL_NONE);
  (void)r;
}
void make_2d(PFN_encodeTiled enc, CUtensorMap* m, const void* ptr, uint64_t rows, uint64_t cols, uint32_t brows, uint32_t bcols, CUtensorMapSwizzle sw) {
  cuuint64_t dims[2] = {cols, rows}, strides[1] = {cols * 2};
  cuuint32_t box[2] = {bcols, brows};
  make_map(enc, m, ptr, 2, dims, strides, box, sw);
}
void make_chunked(PFN_encodeTiled enc, CUtensorMap* m, const void* ptr, uint64_t rows, uint32_t nchunk) {
  cuuint64_t dims[4] = {32, 8, rows / 8, 20}, strides[3] = {64, 8 * 1280, 512};
  cuuint32_t box[4] = {32, 8, 4, nchunk};
  make_map(enc, m, ptr, 4, dims, strides, box, CU_TENSOR_MAP_SWIZZLE_64B);
}

}

extern "C" void kernel_launch(void* const* d_in, const int* in_sizes, int n_in, void* d_out, int out_size) {
  static PFN_encodeTiled enc = nullptr;
  static void *p_ab = nullptr, *p_h = nullptr;
  static int nsm = 0;
  cudaLaunchConfig_t cfg = {};
  cfg.gridDim = dim3(NCTA);
  cfg.blockDim = dim3(384);
  cfg.dynamicSmemBytes = SMEM_TOTAL;
  cfg.stream = cudaStreamPerThread;
  cudaLaunchAttribute attr[1];
  attr[0].id = cudaLaunchAttributeClusterDimension;
  attr[0].val.clusterDim.x = 2; attr[0].val.clusterDim.y = 1; attr[0].val.clusterDim.z = 1;
  cfg.attrs = attr; cfg.numAttrs = 1;
  if (!enc) {
    cudaDriverEntryPointQueryResult st;
    cudaGetDriverEntryPoint("cuTensorMapEncodeTiled", (void**)&enc, cudaEnableDefault, &st);
    cudaGetSymbolAddress(&p_ab, g_ab);
    cudaGetSymbolAddress(&p_h, g_h);
    cudaFuncSetAttribute(fused_kernel, cudaFuncAttributeMaxDynamicSharedMemorySize, SMEM_TOTAL);
    int dev = 0;
    cudaGetDevice(&dev);
    cudaDeviceGetAttribute(&nsm, cudaDevAttrMultiProcessorCount, dev);
  }
  Params P;
  P.xp = (const __nv_bfloat16*)d_in[0];
  P.crp = (const __nv_bfloat16*)d_in[1];
  P.cip = (const __nv_bfloat16*)d_in[2];
  P.wdrp = (const __nv_bfloat16*)d_in[3];
  P.wdip = (const __nv_bfloat16*)d_in[4];
  P.wgp = (const __nv_bfloat16*)d_in[6];
  P.wup = (const __nv_bfloat16*)d_in[7];
  P.wdnp = (const __nv_bfloat16*)d_in[8];
  P.out = (__nv_bfloat16*)d_out;
  if (nsm < NCTA) {
    fb_ln<<<S_, 32, 0, cudaStreamPerThread>>>(P.xp);
    fb_stage1<<<dim3((2 * D_ + F_) / 16, S_ / 16), dim3(16, 16), 0, cudaStreamPerThread>>>(P.wdrp, P.wdip, P.wgp, P.wup);
    fb_stage2<<<dim3(D_ / 16, S_ / 16), dim3(16, 16), 0, cudaStreamPerThread>>>(P.xp, P.crp, P.cip, P.wdnp, P.out);
    return;
  }
  make_2d(enc, &P.x, P.xp, S_, D_, 128, 64, CU_TENSOR_MAP_SWIZZLE_128B);
  {
    cuuint64_t dims[5] = {(cuuint64_t)D_, 2, 4, 4, 20}, strides[4] = {1280, 8 * 1280, 2 * 1280, 32 * 1280};
    cuuint32_t box[5] = {64, 2, 4, 4, 2};
    make_map(enc, &P.wdr, P.wdrp, 5, dims, strides, box, CU_TENSOR_MAP_SWIZZLE_128B);
    make_map(enc, &P.wdi, P.wdip, 5, dims, strides, box, CU_TENSOR_MAP_SWIZZLE_128B);
  }
  {
    cuuint64_t dims[5] = {32, 2, 4, 4, 54 * 640}, strides[4] = {1280, 8 * 1280, 2 * 1280, 64};
    cuuint32_t box[5] = {32, 2, 4, 4, 5};
    make_map(enc, &P.wdn, P.wdnp, 5, dims, strides, box, CU_TENSOR_MAP_SWIZZLE_64B);
  }
  make_2d(enc, &P.wg, P.wgp, D_, F_, 32, 64, CU_TENSOR_MAP_SWIZZLE_128B);
  make_2d(enc, &P.wu, P.wup, D_, F_, 32, 64, CU_TENSOR_MAP_SWIZZLE_128B);
  make_2d(enc, &P.am[0], P.crp, S_, S_, 128, 64, CU_TENSOR_MAP_SWIZZLE_128B);
  make_2d(enc, &P.am[1], P.cip, S_, S_, 128, 64, CU_TENSOR_MAP_SWIZZLE_128B);
  make_2d(enc, &P.crw, P.crp, S_, S_, 32, 256, CU_TENSOR_MAP_SWIZZLE_NONE);
  make_2d(enc, &P.ciw, P.cip, S_, S_, 32, 256, CU_TENSOR_MAP_SWIZZLE_NONE);
  make_2d(enc, &P.am[2], p_h, S_, F_, 128, 64, CU_TENSOR_MAP_SWIZZLE_128B);
  make_chunked(enc, &P.ab, p_ab, 2 * S_, 5);
  make_2d(enc, &P.am[3], P.crp, S_, S_, 64, 64, CU_TENSOR_MAP_SWIZZLE_128B);
  make_2d(enc, &P.am[4], P.cip, S_, S_, 64, 64, CU_TENSOR_MAP_SWIZZLE_128B);

  cudaLaunchKernelEx(&cfg, fused_kernel, P);
}
```
